```python
import torch

def _softmax(x, axis=-1):
    return torch.softmax(x, dim=axis)
def _gelu(x):
    return torch.nn.functional.gelu(x, approximate="tanh")
def _silu(x):
    return torch.nn.functional.silu(x)
def _sigmoid(x):
    return torch.sigmoid(x)
def _layernorm(x, axis=-1, eps=1e-5):
    m = x.mean(dim=axis, keepdim=True)
    v = x.var(dim=axis, keepdim=True, unbiased=False)
    return (x - m) / torch.sqrt(v + eps)
def _scatter_add(tgt, idx, src, axis=0):
    return tgt.clone().index_add_(axis, idx, src)
def _segment_sum(src, seg, n):
    out = torch.zeros((n,) + src.shape[1:], dtype=src.dtype)
    return out.index_add_(0, seg, src)
def _pad(x, pw):
    flat = tuple(v for pair in reversed(pw) for v in pair)
    return torch.nn.functional.pad(x, flat)

kernel_name = 'concat_heads__sliding_block_cached__sliding_block_cached__decode'

def setup_inputs():

    _w = (lambda a: (lambda t: t.to(torch.bfloat16) if t.is_floating_point() else t)(torch.as_tensor(a)))
    def _A_setup():
        B, Sq, D = 4, 1, 576
        Hq, Hkv, Sk, Dh = 32, 16, 8192, 128
        assert Hq % Hkv == 0, (Hq, Hkv)
        return {
            "x": _w((lambda *s: torch.randn(*s, dtype=torch.bfloat16) * 0.8)(B, Sq, D)),
            "k_cache": _w((lambda *s: torch.randn(*s, dtype=torch.bfloat16) * 0.8)(B, Hkv, Sk, Dh)),
            "v_cache": _w((lambda *s: torch.randn(*s, dtype=torch.bfloat16) * 0.05)(B, Hkv, Sk, Dh)),
            "wq": _w((lambda *s: torch.randn(*s, dtype=torch.bfloat16) * 0.8)(D, Hq * Dh) * (D ** -0.5)),
            "wo": _w((lambda *s: torch.randn(*s, dtype=torch.bfloat16) * 0.05)(Hq * Dh, D) * ((Hq * Dh) ** -0.5)),
        }
    _A_in = _A_setup()

    def _B_setup():
        B, Sq, D = 4, 1, 576
        Hq, Hkv, Sk, Dh = 32, 16, 8192, 128
        assert Hq % Hkv == 0, (Hq, Hkv)
        return {
            "x": _w((lambda *s: torch.randn(*s, dtype=torch.bfloat16) * 0.8)(B, Sq, D)),
            "k_cache": _w((lambda *s: torch.randn(*s, dtype=torch.bfloat16) * 0.8)(B, Hkv, Sk, Dh)),
            "v_cache": _w((lambda *s: torch.randn(*s, dtype=torch.bfloat16) * 0.05)(B, Hkv, Sk, Dh)),
            "wq": _w((lambda *s: torch.randn(*s, dtype=torch.bfloat16) * 0.8)(D, Hq * Dh) * (D ** -0.5)),
            "wo": _w((lambda *s: torch.randn(*s, dtype=torch.bfloat16) * 0.05)(Hq * Dh, D) * ((Hq * Dh) ** -0.5)),
        }
    _B_in = _B_setup()

    return {
        "A_x": _A_in["x"],
        "A_k_cache": _A_in["k_cache"],
        "A_v_cache": _A_in["v_cache"],
        "A_wq": _A_in["wq"],
        "A_wo": _A_in["wo"],
        "B_x": _B_in["x"],
        "B_k_cache": _B_in["k_cache"],
        "B_v_cache": _B_in["v_cache"],
        "B_wq": _B_in["wq"],
        "B_wo": _B_in["wo"],
    }

def reference(A_x, A_k_cache, A_v_cache, A_wq, A_wo, B_x, B_k_cache, B_v_cache, B_wq, B_wo):
    def _A_ref(x, k_cache, v_cache, wq, wo):
        B, Sq, D = x.shape
        Hq, Dh = 32, 128
        Hkv, Sk = k_cache.shape[1], k_cache.shape[2]
        W = min(4096, max(256, Sk // 4))
        rep = Hq // Hkv
        q = (lambda x, *d: x.permute(*d))((x @ wq).reshape(B, Sq, Hq, Dh), 0, 2, 1, 3)
        k = (lambda x, n, axis: torch.repeat_interleave(x, n, dim=axis))(k_cache[:, :, Sk - W:, :], rep, axis=1)
        v = (lambda x, n, axis: torch.repeat_interleave(x, n, dim=axis))(v_cache[:, :, Sk - W:, :], rep, axis=1)
        scores = torch.einsum("bhqd,bhkd->bhqk", q, k) * (Dh ** -0.5)
        p = _softmax(scores, axis=-1)
        o = torch.einsum("bhqk,bhkd->bhqd", p, v)
        return (lambda x, *d: x.permute(*d))(o, 0, 2, 1, 3).reshape(B, Sq, Hq * Dh) @ wo

    def _B_ref(x, k_cache, v_cache, wq, wo):
        B, Sq, D = x.shape
        Hq, Dh = 32, 128
        Hkv, Sk = k_cache.shape[1], k_cache.shape[2]
        W = min(4096, max(256, Sk // 4))
        rep = Hq // Hkv
        q = (lambda x, *d: x.permute(*d))((x @ wq).reshape(B, Sq, Hq, Dh), 0, 2, 1, 3)
        k = (lambda x, n, axis: torch.repeat_interleave(x, n, dim=axis))(k_cache[:, :, Sk - W:, :], rep, axis=1)
        v = (lambda x, n, axis: torch.repeat_interleave(x, n, dim=axis))(v_cache[:, :, Sk - W:, :], rep, axis=1)
        scores = torch.einsum("bhqd,bhkd->bhqk", q, k) * (Dh ** -0.5)
        p = _softmax(scores, axis=-1)
        o = torch.einsum("bhqk,bhkd->bhqd", p, v)
        return (lambda x, *d: x.permute(*d))(o, 0, 2, 1, 3).reshape(B, Sq, Hq * Dh) @ wo

    a = _A_ref(A_x, A_k_cache, A_v_cache, A_wq, A_wo)
    b = _B_ref(B_x, B_k_cache, B_v_cache, B_wq, B_wo)
    return torch.concatenate([a, b], axis=-1)
```

```cpp
#include <cuda_runtime.h>
#include <cuda.h>
#include <cuda_bf16.h>
#include <stdint.h>

#define POLL_SLEEP 32
#define OPOLL_AFTER 1
#define WSUB 2
#define VSUB_FROM 56
#define BRX 16
#define SWAP24 1
#define WO_PROMO CU_TENSOR_MAP_L2_PROMOTION_L2_128B
#define GATE 100
#define GATE_PACE (WO_PACE / WSUB)
#define WO_GAP 0
#define WO_PACE ((PACE_NS * 9) / 8)
#define DEPHASE 0
#define PACE_NS 655
#define PACE_T0 2400

namespace {

constexpr int D_MODEL = 576;
constexpr int HKV = 16;
constexpr int SK = 8192;
constexpr int WIN = 2048;
constexpr int NCTA = 128;
constexpr int NWARP = 8;
constexpr int NTHREADS = (NWARP + 1 + 4) * 32;
constexpr int TILE_BYTES = 16384;
constexpr int TPW = WIN / 64 / NWARP;
constexpr int NTILES = 2 * WIN / 64;
constexpr int WQ_CH = 3, WQ_ROWS = 192, WQ_BYTES = WQ_ROWS * 128;
constexpr int WO_PITCH = 288;
constexpr int WO_CH = 4, WO_ROWS = 256 / WO_CH, WO_BYTES = WO_ROWS * WO_PITCH;
constexpr int X_PITCH = 1168, O_PITCH = 576;

constexpr int SM_W = 0;
constexpr int SM_X = SM_W + 256 * WO_PITCH;
constexpr int SM_QS = SM_X + 4 * X_PITCH;
constexpr int SM_OS = SM_QS + 512;
constexpr int SM_ML = SM_OS + 4 * O_PITCH;
constexpr int SM_EP = SM_ML + NWARP * 16;
constexpr int SM_BAR = SM_EP + 16;
constexpr int BAR_FULL = 0, BAR_EMPTY = 8, BAR_WQ = 16, BAR_WO = 19, BAR_ML = BAR_WO + WO_CH, BAR_O = BAR_ML + 1, NBAR = BAR_O + 4;
constexpr int SM_FIXED = SM_BAR + NBAR * 8;
constexpr int SM_TOTAL = SM_FIXED + 2047 + NWARP * TILE_BYTES;
constexpr uint64_t EVICT_FIRST = 0x12F0000000000000ull;

struct Params {
    CUtensorMap wq[2];
    CUtensorMap wo[2];
    const __nv_bfloat16* x[2];
    const __nv_bfloat16* k[2];
    const __nv_bfloat16* v[2];
    __nv_bfloat16* out;
    unsigned long long* qx;
    unsigned long long* ox;
    unsigned int* epoch;
};

__device__ __align__(128) unsigned long long g_qx[32 * 4 * 128];
__device__ __align__(128) unsigned long long g_ox[32 * 4 * 128];
__device__ unsigned int g_epoch[NCTA];

#define TS(i)
#define TSG(i)

__device__ __forceinline__ uint32_t smem_u32(const void* p) { return (uint32_t)__cvta_generic_to_shared(p); }

__device__ __forceinline__ void mbar_init(uint32_t bar, uint32_t cnt) {
    asm volatile("mbarrier.init.shared::cta.b64 [%0], %1;" ::"r"(bar), "r"(cnt) : "memory");
}
__device__ __forceinline__ void mbar_expect_tx(uint32_t bar, uint32_t bytes) {
    asm volatile("mbarrier.arrive.expect_tx.shared::cta.b64 _, [%0], %1;" ::"r"(bar), "r"(bytes) : "memory");
}
__device__ __forceinline__ void mbar_arrive(uint32_t bar) {
    asm volatile("mbarrier.arrive.shared::cta.b64 _, [%0];" ::"r"(bar) : "memory");
}
__device__ __forceinline__ void mbar_wait(uint32_t bar, uint32_t parity) {
#pragma unroll 1
    for (int it = 0; it < (1 << 22); ++it) {
        uint32_t ok;
        asm volatile(
            "{\n.reg .pred p;\n"
            "mbarrier.try_wait.parity.shared::cta.b64 p, [%1], %2;\n"
            "selp.u32 %0, 1, 0, p;\n}\n"
            : "=r"(ok) : "r"(bar), "r"(parity) : "memory");
        if (ok) break;
    }
}
__device__ __forceinline__ bool mbar_test(uint32_t bar, uint32_t parity) {
    uint32_t ok;
    asm volatile(
        "{\n.reg .pred p;\n"
        "mbarrier.test_wait.parity.shared::cta.b64 p, [%1], %2;\n"
        "selp.u32 %0, 1, 0, p;\n}\n"
        : "=r"(ok) : "r"(bar), "r"(parity) : "memory");
    return ok != 0;
}
__device__ __forceinline__ void bulk_load(uint32_t dst, const void* src, uint32_t bytes, uint32_t bar, uint64_t pol) {
    asm volatile(
        "cp.async.bulk.shared::cluster.global.mbarrier::complete_tx::bytes.L2::cache_hint [%0], [%1], %2, [%3], %4;"
        ::"r"(dst), "l"(src), "r"(bytes), "r"(bar), "l"(pol) : "memory");
}
__device__ __forceinline__ void tma_load_2d(uint32_t dst, const CUtensorMap* tm, int c0, int c1, uint32_t bar, uint64_t pol) {
    asm volatile(
        "cp.async.bulk.tensor.2d.shared::cluster.global.mbarrier::complete_tx::bytes.L2::cache_hint "
        "[%0], [%1, {%3, %4}], [%2], %5;"
        ::"r"(dst), "l"(tm), "r"(bar), "r"(c0), "r"(c1), "l"(pol) : "memory");
}
__device__ __forceinline__ void wait_until(uint32_t t) {
#pragma unroll 1
    for (int it = 0; it < (1 << 20); ++it) {
        uint32_t now;
        asm volatile("mov.u32 %0, %globaltimer_lo;" : "=r"(now));
        if ((int)(now - t) >= 0) break;
    }
}
__device__ __forceinline__ void consumer_sync() { asm volatile("bar.sync 1, 256;" ::: "memory"); }

__device__ __forceinline__ void ldsm_x4(uint32_t (&r)[4], uint32_t addr) {
    asm volatile("ldmatrix.sync.aligned.m8n8.x4.shared.b16 {%0,%1,%2,%3}, [%4];"
                 : "=r"(r[0]), "=r"(r[1]), "=r"(r[2]), "=r"(r[3]) : "r"(addr) : "memory");
}
__device__ __forceinline__ void ldsm_x4_t(uint32_t (&r)[4], uint32_t addr) {
    asm volatile("ldmatrix.sync.aligned.m8n8.x4.trans.shared.b16 {%0,%1,%2,%3}, [%4];"
                 : "=r"(r[0]), "=r"(r[1]), "=r"(r[2]), "=r"(r[3]) : "r"(addr) : "memory");
}
__device__ __forceinline__ void mma16816(float (&d)[4], uint32_t a0, uint32_t a1, uint32_t a2, uint32_t a3,
                                         uint32_t b0, uint32_t b1) {
    asm volatile(
        "mma.sync.aligned.m16n8k16.row.col.f32.bf16.bf16.f32 {%0,%1,%2,%3}, {%4,%5,%6,%7}, {%8,%9}, {%0,%1,%2,%3};"
        : "+f"(d[0]), "+f"(d[1]), "+f"(d[2]), "+f"(d[3])
        : "r"(a0), "r"(a1), "r"(a2), "r"(a3), "r"(b0), "r"(b1));
}
__device__ __forceinline__ float ex2(float x) {
    float y;
    asm("ex2.approx.ftz.f32 %0, %1;" : "=f"(y) : "f"(x));
    return y;
}
__device__ __forceinline__ uint32_t pack_bf16(float lo, float hi) {
    uint32_t r;
    asm("cvt.rn.bf16x2.f32 %0, %1, %2;" : "=r"(r) : "f"(hi), "f"(lo));
    return r;
}
__device__ __forceinline__ void ll_store(unsigned long long* p, uint32_t data, uint32_t tag) {
    asm volatile("{\n.reg .b64 v;\nmov.b64 v, {%1, %2};\nst.relaxed.gpu.global.b64 [%0], v;\n}" ::"l"(p), "r"(data), "r"(tag) : "memory");
}
__device__ __forceinline__ void ld_v4(uint32_t (&d)[4], const uint32_t* p) {
    asm volatile("ld.relaxed.gpu.global.v4.b32 {%0, %1, %2, %3}, [%4];"
                 : "=r"(d[0]), "=r"(d[1]), "=r"(d[2]), "=r"(d[3]) : "l"(p) : "memory");
}
constexpr int SPIN_MAX = 1 << 21;
__device__ __forceinline__ uint32_t ll_wait(const unsigned long long* p, uint32_t tag) {
    uint32_t d = 0, f;
#pragma unroll 1
    for (int it = 0; it < SPIN_MAX; ++it) {
        asm volatile("{\n.reg .b64 v;\nld.relaxed.gpu.global.b64 v, [%2];\nmov.b64 {%0, %1}, v;\n}" : "=r"(d), "=r"(f) : "l"(p) : "memory");
        if (f == tag) break;
        if (POLL_SLEEP) __nanosleep(POLL_SLEEP);
    }
    return d;
}

__global__ void __launch_bounds__(NTHREADS, 1) fused_decode_kernel(const __grid_constant__ Params p) {
    extern __shared__ __align__(1024) unsigned char smem[];
    const uint32_t sb = smem_u32(smem);
    const uint32_t bars = sb + SM_BAR;
    if (threadIdx.x == 0) {
        const CUtensorMap* tmq = &p.wq[blockIdx.x >> 6];
#pragma unroll
        for (int c = 0; c < WQ_CH; ++c) {
            mbar_init(bars + (BAR_WQ + c) * 8, 1);
            asm volatile("fence.mbarrier_init.release.cluster;" ::: "memory");
            mbar_expect_tx(bars + (BAR_WQ + c) * 8, WQ_BYTES);
            tma_load_2d(sb + SM_W + c * WQ_BYTES, tmq, (blockIdx.x & 63) * 64, c * WQ_ROWS, bars + (BAR_WQ + c) * 8, EVICT_FIRST);
        }
    }
    uint32_t tstart = 0;
    if ((threadIdx.x >> 5) == NWARP) {
        asm volatile("mov.u32 %0, %globaltimer_lo;" : "=r"(tstart));
    } else if (threadIdx.x >= 32 && threadIdx.x < 352) {
        const uint32_t xi = threadIdx.x - (threadIdx.x < 256 ? 32 : 64);
        asm volatile("cp.async.cg.shared.global [%0], [%1], 16;"
                     ::"r"(sb + SM_X + (xi / 72u) * 16 + xi * 16), "l"((const char*)p.x[blockIdx.x >> 6] + xi * 16) : "memory");
    } else if (threadIdx.x == 352) {
        asm volatile("cp.async.ca.shared.global [%0], [%1], 4;" ::"r"(sb + SM_EP), "l"(p.epoch + blockIdx.x) : "memory");
    }
    const uint32_t ring = (sb + SM_FIXED + 2047u) & ~2047u;
    unsigned char* const ringp = smem + (ring - sb);
    const int tid = threadIdx.x, w = tid >> 5, lane = tid & 31;
    const int g = lane >> 2, t = lane & 3;
    const int mat = lane >> 3, i8 = lane & 7;
    const int cta = blockIdx.x;
    const int br = cta >> 6, kvh = (cta >> 2) & 15, b = cta & 3;
    const int grp = cta >> 2;
    __nv_bfloat16* out_dst = p.out + (g & 3) * 1152 + br * 576 + b * 144 + w * 16 + (g >> 2) * 8 + 2 * t;
    if (kvh == 0 && w <= NWARP) asm volatile("st.relaxed.gpu.global.b32 [%0], %1;" ::"l"(out_dst), "r"(0) : "memory");
    uint32_t tag;
    TSG(22);
    TS(0);

    if (w > NWARP) {
        const int c = w - NWARP - 1, l16 = lane & 15;
        const int s0 = (b + 1 + (lane >> 4)) & 3, s1 = (b + 3) & 3;
        const uint32_t* src0 = (const uint32_t*)(p.ox + (grp * 4 + s0) * 128 + c * 32) + l16 * 4;
        const uint32_t* src1 = (const uint32_t*)(p.ox + (grp * 4 + s1) * 128 + c * 32) + l16 * 4;
        const uint32_t dst0 = sb + SM_OS + s0 * O_PITCH + c * 128 + l16 * 8, dst1 = sb + SM_OS + s1 * O_PITCH + c * 128 + l16 * 8;
        asm volatile("cp.async.wait_all;" ::: "memory");
        asm volatile("bar.sync 2, %0;" ::"n"(NTHREADS) : "memory");
        tag = *(const volatile uint32_t*)(smem + SM_EP) + 1u;
        if (tag == 0u) tag = 1u;
        mbar_wait(bars + (BAR_WO + OPOLL_AFTER) * 8, 0);
        uint32_t d0[4], d1[4];
#pragma unroll 1
        for (int it = 0; it < SPIN_MAX; ++it) {
            ld_v4(d0, src0);
            ld_v4(d1, src1);
            if (__all_sync(0xffffffffu, d0[1] == tag && d0[3] == tag && d1[1] == tag && d1[3] == tag)) break;
            if (POLL_SLEEP) __nanosleep(POLL_SLEEP);
        }
        asm volatile("st.shared.v2.b32 [%0], {%1, %2};" ::"r"(dst0), "r"(d0[0]), "r"(d0[2]) : "memory");
        asm volatile("st.shared.v2.b32 [%0], {%1, %2};" ::"r"(dst1), "r"(d1[0]), "r"(d1[2]) : "memory");
        __syncwarp();
        if (lane == 0) mbar_arrive(bars + (BAR_O + c) * 8);
        return;
    }
    if (w == NWARP) {
        const size_t kvoff = ((size_t)(b * HKV + kvh) * SK + (SK - WIN)) * 256;
        const char* kbase = (const char*)p.k[br] + kvoff;
        const char* vbase = (const char*)p.v[br] + kvoff - (size_t)(NTILES / 2) * TILE_BYTES;
        const CUtensorMap* tmo = &p.wo[br];
        if (lane == 0) {
#pragma unroll
            for (int i = 0; i < BAR_ML; ++i)
                if (i < BAR_WQ || i >= BAR_WO) mbar_init(bars + i * 8, 1);
            mbar_init(bars + BAR_ML * 8, NWARP);
#pragma unroll
            for (int c = 0; c < 4; ++c) mbar_init(bars + (BAR_O + c) * 8, 2);
            asm volatile("fence.mbarrier_init.release.cluster;" ::: "memory");
            asm volatile("prefetch.tensormap [%0];" ::"l"(tmo) : "memory");
        }
        __syncwarp();
        asm volatile("bar.arrive 2, %0;" ::"n"(NTHREADS) : "memory");
        TS(21);
        if (lane == 0) {
            uint32_t tnext = tstart + PACE_T0 + (DEPHASE * (grp - 16)) / 32;
#pragma unroll 1
            for (int n = 0; n < NTILES; ++n) {
                const int s = n & 7;
                if (n >= 8) mbar_wait(bars + (BAR_EMPTY + s) * 8, ((n >> 3) - 1) & 1);
                mbar_expect_tx(bars + (BAR_FULL + s) * 8, TILE_BYTES);
                const char* src = (n < NTILES / 2 ? kbase : vbase) + (size_t)((SWAP24 ? ((n & 0x2b) | ((n & 4) << 2) | ((n & 16) >> 2)) : n) ^ (br * BRX)) * TILE_BYTES;
                wait_until(tnext);
                if (n < VSUB_FROM) {
                    bulk_load(ring + s * TILE_BYTES, src, TILE_BYTES, bars + (BAR_FULL + s) * 8, EVICT_FIRST);
                } else {
                    bulk_load(ring + s * TILE_BYTES, src, TILE_BYTES / 2, bars + (BAR_FULL + s) * 8, EVICT_FIRST);
                    wait_until(tnext + PACE_NS / 2);
                    bulk_load(ring + s * TILE_BYTES + TILE_BYTES / 2, src + TILE_BYTES / 2, TILE_BYTES / 2, bars + (BAR_FULL + s) * 8, EVICT_FIRST);
                }
                tnext += PACE_NS;
            }
            tnext += WO_GAP;
            uint32_t step = WO_PACE / WSUB;
#pragma unroll 1
            for (int c = 0; c < WO_CH * WSUB; ++c) {
                if (c % WSUB == 0) mbar_expect_tx(bars + (BAR_WO + c / WSUB) * 8, WO_BYTES);
                if (c == GATE && !mbar_test(bars + (BAR_FULL + 7) * 8, 1)) {
                    mbar_wait(bars + (BAR_FULL + 7) * 8, 1);
                    uint32_t now;
                    asm volatile("mov.u32 %0, %globaltimer_lo;" : "=r"(now));
                    if ((int)(now - tnext) > 0) { tnext = now; step = GATE_PACE; }
                }
                wait_until(tnext);
                tnext += step;
                if (c == 0) TS(12);
                tma_load_2d(sb + SM_W + c * (WO_BYTES / WSUB), tmo, b * 144, kvh * 256 + c * (WO_ROWS / WSUB),
                            bars + (BAR_WO + c / WSUB) * 8, EVICT_FIRST);
            }
        }
        __syncwarp();
        tag = *(const volatile uint32_t*)(smem + SM_EP) + 1u;
        if (tag == 0u) tag = 1u;
    } else {
        unsigned long long* const qx_dst = p.qx + (grp * 4 + (g & 3)) * 128 + b * 32 + w * 4 + t;
        const int opos = (tid & 112) + (tid & 3) * 4 + ((tid >> 2) & 3);
        unsigned long long* const ox_dst = p.ox + (grp * 4 + b) * 128 + opos;
        {
            if (g < 4) ll_store(qx_dst, 0u, 0u);
            if (tid < 128) ll_store(ox_dst, 0u, 0u);
            asm volatile("cp.async.wait_all;" ::: "memory");
            asm volatile("bar.sync 2, %0;" ::"n"(NTHREADS) : "memory");
        }
        tag = *(const volatile uint32_t*)(smem + SM_EP) + 1u;
        if (tag == 0u) tag = 1u;
        if (tid == 64) p.epoch[cta] = tag;
        TS(1);

        {
            float qa[4] = {0.f, 0.f, 0.f, 0.f}, qb[4] = {0.f, 0.f, 0.f, 0.f};
            uint32_t xaddr = sb + SM_X + (i8 & 3) * X_PITCH + mat * 16;
            uint32_t waddr = sb + SM_W + lane * 128 + ((w ^ i8) << 4);
#pragma unroll 1
            for (int c = 0; c < WQ_CH; ++c) {
                mbar_wait(bars + (BAR_WQ + c) * 8, 0);
                if (c == WQ_CH - 1) TS(2);
#pragma unroll
                for (int kk = 0; kk < WQ_ROWS / 32; ++kk) {
                    uint32_t xa[4], wb[4];
                    ldsm_x4(xa, xaddr + kk * 64);
                    ldsm_x4_t(wb, waddr + kk * 32 * 128);
                    mma16816(qa, xa[0], xa[0], xa[1], xa[1], wb[0], wb[1]);
                    mma16816(qb, xa[2], xa[2], xa[3], xa[3], wb[2], wb[3]);
                }
                xaddr += WQ_ROWS * 2;
                waddr += WQ_BYTES;
            }
            if (g < 4) ll_store(qx_dst, pack_bf16(qa[0] + qb[0], qa[1] + qb[1]), tag);
        }
        TS(19);
        if (tid < 128) {
            const uint32_t qw = ll_wait(p.qx + (grp * 4 + b) * 128 + tid, tag);
            ((uint32_t*)(smem + SM_QS))[tid] = qw;
        }
        consumer_sync();
        TS(3);

        uint32_t qf[2][16];
        {
            const uint32_t* qs = (const uint32_t*)(smem + SM_QS);
#pragma unroll
            for (int h = 0; h < 2; ++h)
#pragma unroll
                for (int c = 0; c < 16; ++c) qf[h][c] = qs[h * 64 + ((c ^ g) << 2) + t];
        }

        const uint32_t slot = ring + w * TILE_BYTES;
        const uint32_t bfull = bars + (BAR_FULL + w) * 8, bempty = bars + (BAR_EMPTY + w) * 8;
        const uint32_t lbase = slot + ((mat & 1) * 8 + i8) * 256 + (((mat >> 1) ^ i8) << 4);
        const int myj = t ^ (g >> 1);
        const bool odd = (g & 1) != 0;

        float sc[TPW][4];
#pragma unroll
        for (int i = 0; i < TPW; ++i) sc[i][0] = sc[i][1] = sc[i][2] = sc[i][3] = 0.f;
#pragma unroll 1
        for (int i = 0; i < TPW; ++i) {
            mbar_wait(bfull, i & 1);
            float s00 = 0.f, s10 = 0.f, s01 = 0.f, s11 = 0.f;
#pragma unroll
            for (int j = 0; j < 4; ++j) {
                float d0[4] = {0.f, 0.f, 0.f, 0.f}, d1[4] = {0.f, 0.f, 0.f, 0.f};
#pragma unroll
                for (int s = 0; s < 8; ++s) {
                    uint32_t a[4];
                    ldsm_x4(a, (lbase ^ (32 * (s ^ j))) + 4096 * j);
                    mma16816(d0, a[0], a[1], a[2], a[3], qf[0][2 * s], qf[0][2 * s + 1]);
                    mma16816(d1, a[0], a[1], a[2], a[3], qf[1][2 * s], qf[1][2 * s + 1]);
                }
                if (j == myj) {
                    s00 = odd ? d0[1] : d0[0];
                    s01 = odd ? d0[3] : d0[2];
                    s10 = odd ? d1[1] : d1[0];
                    s11 = odd ? d1[3] : d1[2];
                }
            }
            __syncwarp();
            if (lane == 0) mbar_arrive(bempty);
#pragma unroll
            for (int u = 0; u + 1 < TPW; ++u) {
#pragma unroll
                for (int q = 0; q < 4; ++q) sc[u][q] = sc[u + 1][q];
            }
            sc[TPW - 1][0] = s00; sc[TPW - 1][1] = s10; sc[TPW - 1][2] = s01; sc[TPW - 1][3] = s11;
        }
        TS(4);

        const float cs = 0.08838834764831845f * 1.4426950408889634f;
        float m0 = -INFINITY, m1 = -INFINITY;
#pragma unroll
        for (int i = 0; i < TPW; ++i) {
            m0 = fmaxf(m0, fmaxf(sc[i][0], sc[i][2]));
            m1 = fmaxf(m1, fmaxf(sc[i][1], sc[i][3]));
        }
#pragma unroll
        for (int o = 16; o > 0; o >>= 1) {
            m0 = fmaxf(m0, __shfl_xor_sync(0xffffffffu, m0, o));
            m1 = fmaxf(m1, __shfl_xor_sync(0xffffffffu, m1, o));
        }
        m0 *= cs; m1 *= cs;
        float l0 = 0.f, l1 = 0.f;
        uint32_t pa[TPW][4];
#pragma unroll
        for (int i = 0; i < TPW; ++i) {
#pragma unroll
            for (int q = 0; q < 4; ++q) {
                const float pv = ex2(fmaf(sc[i][q], cs, (q & 1) ? -m1 : -m0));
                if (q & 1) l1 += pv; else l0 += pv;
                pa[i][q] = pack_bf16(pv, pv);
            }
        }
#pragma unroll
        for (int o = 16; o > 0; o >>= 1) {
            l0 += __shfl_xor_sync(0xffffffffu, l0, o);
            l1 += __shfl_xor_sync(0xffffffffu, l1, o);
        }
        if (lane == 0) {
            ((float4*)(smem + SM_ML))[w] = make_float4(m0, l0, m1, l1);
            mbar_arrive(bars + BAR_ML * 8);
        }

        const uint32_t halfmask = odd ? 0xffff0000u : 0x0000ffffu;
        float f0 = 0.f, f1 = 0.f;
        float acc[16][4];
#pragma unroll
        for (int c = 0; c < 16; ++c) { acc[c][0] = acc[c][1] = acc[c][2] = acc[c][3] = 0.f; }
#pragma unroll 1
        for (int i = 0; i < TPW; ++i) {
            if (i == TPW - 1) {
                mbar_wait(bars + BAR_ML * 8, 0);
                const float4 mine = ((const float4*)(smem + SM_ML))[i8];
                float M0 = mine.x, M1 = mine.z;
#pragma unroll
                for (int o = 4; o > 0; o >>= 1) {
                    M0 = fmaxf(M0, __shfl_xor_sync(0xffffffffu, M0, o));
                    M1 = fmaxf(M1, __shfl_xor_sync(0xffffffffu, M1, o));
                }
                float L0 = ex2(mine.x - M0) * mine.y, L1 = ex2(mine.z - M1) * mine.w;
#pragma unroll
                for (int o = 4; o > 0; o >>= 1) {
                    L0 += __shfl_xor_sync(0xffffffffu, L0, o);
                    L1 += __shfl_xor_sync(0xffffffffu, L1, o);
                }
                f0 = __fdividef(ex2(m0 - M0), L0);
                f1 = __fdividef(ex2(m1 - M1), L1);
            }
            mbar_wait(bfull, i & 1);
            if (i == TPW - 1) TS(5);
#pragma unroll
            for (int j = 0; j < 4; ++j) {
                const uint32_t msk = (j == myj) ? halfmask : 0u;
                const uint32_t a0 = pa[0][0] & msk, a1 = pa[0][1] & msk, a2 = pa[0][2] & msk, a3 = pa[0][3] & msk;
#pragma unroll
                for (int s = 0; s < 8; ++s) {
                    uint32_t bb[4];
                    ldsm_x4_t(bb, (lbase ^ (32 * (s ^ j)) ^ (512 * j)) + 4096 * j);
                    mma16816(acc[2 * s], a0, a1, a2, a3, bb[0], bb[1]);
                    mma16816(acc[2 * s + 1], a0, a1, a2, a3, bb[2], bb[3]);
                }
            }
            __syncwarp();
            if (lane == 0) mbar_arrive(bempty);
#pragma unroll
            for (int u = 0; u + 1 < TPW; ++u) {
#pragma unroll
                for (int q = 0; q < 4; ++q) pa[u][q] = pa[u + 1][q];
            }
        }
        TS(6);

#pragma unroll
        for (int c = 0; c < 16; ++c)
            if ((c & 4) == 0) {
#pragma unroll
                for (int q = 0; q < 4; ++q) acc[c][q] += __shfl_xor_sync(0xffffffffu, acc[c ^ 4][q], 16);
            }
#pragma unroll
        for (int c = 0; c < 16; ++c)
            if ((c & 6) == 0) {
#pragma unroll
                for (int q = 0; q < 4; ++q) acc[c][q] += __shfl_xor_sync(0xffffffffu, acc[c ^ 2][q], 8);
            }
#pragma unroll
        for (int c = 0; c < 16; c += 8) {
#pragma unroll
            for (int q = 0; q < 4; ++q) acc[c][q] += __shfl_xor_sync(0xffffffffu, acc[c ^ 1][q], 4);
        }
        {
            float2* ow = (float2*)(ringp + w * TILE_BYTES);
            ow[lane] = make_float2(acc[0][0] * f0, acc[0][1] * f0);
            ow[32 + lane] = make_float2(acc[8][0] * f0, acc[8][1] * f0);
            ow[64 + lane] = make_float2(acc[0][2] * f1, acc[0][3] * f1);
            ow[96 + lane] = make_float2(acc[8][2] * f1, acc[8][3] * f1);
        }
        TS(13);
        consumer_sync();
        TS(7);
        if (tid < 128) {
            float o0 = 0.f, o1 = 0.f;
#pragma unroll
            for (int ww = 0; ww < NWARP; ++ww) {
                const float2 v = ((const float2*)(ringp + ww * TILE_BYTES))[tid];
                o0 += v.x; o1 += v.y;
            }
            const uint32_t ow = pack_bf16(o0, o1);
            ll_store(ox_dst, ow, tag);
            ((uint32_t*)(smem + SM_OS + b * O_PITCH))[opos] = ow;
            __syncwarp();
            if (lane == 0) mbar_arrive(bars + (BAR_O + w) * 8);
        }
        TS(14);
    }
    {
        uint32_t abase = sb + SM_W + ((mat >> 1) * 8 + i8) * WO_PITCH + (((mat & 1) ^ (i8 >> 2)) << 4) + w * 32;
        const uint32_t ouse = (g < 4) == (t < 2);
        uint32_t old = sb + SM_OS + (g & 3) * O_PITCH + t * 16;
        asm volatile("" : "+r"(abase), "+r"(old), "+l"(out_dst));
        uint32_t wa[4][4][4], ob[4][2][4];
        float oa[4][4];
#pragma unroll
        for (int i = 0; i < 4; ++i) {
            oa[i][0] = oa[i][1] = oa[i][2] = oa[i][3] = 0.f;
#pragma unroll
            for (int u = 0; u < 2; ++u) ob[i][u][0] = ob[i][u][1] = ob[i][u][2] = ob[i][u][3] = 0u;
        }
        auto load_w = [&](int c) {
#pragma unroll
            for (int kk = 0; kk < 4; ++kk) ldsm_x4_t(wa[c][kk], abase + (c * 4 + kk) * 16 * WO_PITCH);
        };
        auto load_o = [&](int c) {
#pragma unroll
            for (int u = 0; u < 2; ++u)
                asm volatile("{\n.reg .pred p;\nsetp.ne.u32 p, %5, 0;\n@p ld.shared.v4.b32 {%0, %1, %2, %3}, [%4];\n}"
                             : "+r"(ob[c][u][0]), "+r"(ob[c][u][1]), "+r"(ob[c][u][2]), "+r"(ob[c][u][3])
                             : "r"(old + c * 128 + u * 64), "r"(ouse) : "memory");
        };
        auto mul = [&](int c) {
#pragma unroll
            for (int kk = 0; kk < 4; ++kk)
                mma16816(oa[kk], wa[c][kk][0], wa[c][kk][1], wa[c][kk][2], wa[c][kk][3], ob[c][kk >> 1][(kk & 1) * 2],
                         ob[c][kk >> 1][(kk & 1) * 2 + 1]);
        };
        mbar_wait(bars + (BAR_WO + 0) * 8, 0);
        load_w(0);
        mbar_wait(bars + (BAR_WO + 1) * 8, 0);
        load_w(1);
        TS(15);
        bool o0 = false, o1 = false, o2 = false, o3 = false, w2 = false, w3 = false;
#pragma unroll 1
        for (int it = 0; it < (1 << 24); ++it) {
            if (!o0 && mbar_test(bars + (BAR_O + 0) * 8, 0)) { load_o(0); mul(0); o0 = true; }
            if (!o1 && mbar_test(bars + (BAR_O + 1) * 8, 0)) { load_o(1); mul(1); o1 = true; }
            if (!o2 && mbar_test(bars + (BAR_O + 2) * 8, 0)) { load_o(2); o2 = true; }
            if (!o3 && mbar_test(bars + (BAR_O + 3) * 8, 0)) { load_o(3); o3 = true; }
            if (o0 && o1 && o2 && o3) break;
            if (!w2) {
                if (mbar_test(bars + (BAR_WO + 2) * 8, 0)) { load_w(2); w2 = true; }
            } else if (mbar_test(bars + (BAR_WO + 3) * 8, 0)) {
                load_w(3);
                w3 = true;
                break;
            }
        }
        TS(8);
        if (!w3) {
            if (!w2) { mbar_wait(bars + (BAR_WO + 2) * 8, 0); load_w(2); }
            mul(2);
            mbar_wait(bars + (BAR_WO + 3) * 8, 0);
            load_w(3);
            mul(3);
        } else {
            if (o2) mul(2);
            if (o3) mul(3);
            if (!o0) { mbar_wait(bars + (BAR_O + 0) * 8, 0); load_o(0); mul(0); }
            if (!o1) { mbar_wait(bars + (BAR_O + 1) * 8, 0); load_o(1); mul(1); }
            if (!o2) { mbar_wait(bars + (BAR_O + 2) * 8, 0); load_o(2); mul(2); }
            if (!o3) { mbar_wait(bars + (BAR_O + 3) * 8, 0); load_o(3); mul(3); }
        }
        const float r0 = ((oa[0][0] + oa[1][0]) + (oa[2][0] + oa[3][0])) +
                         __shfl_xor_sync(0xffffffffu, (oa[0][2] + oa[1][2]) + (oa[2][2] + oa[3][2]), 2);
        const float r1 = ((oa[0][1] + oa[1][1]) + (oa[2][1] + oa[3][1])) +
                         __shfl_xor_sync(0xffffffffu, (oa[0][3] + oa[1][3]) + (oa[2][3] + oa[3][3]), 2);
        uint32_t rt;
        asm volatile("movmatrix.sync.aligned.m8n8.trans.b16 %0, %1;" : "=r"(rt) : "r"(pack_bf16(r0, r1)));
        asm volatile("red.relaxed.gpu.global.add.noftz.bf16x2 [%0], %1;" ::"l"(out_dst), "r"(rt) : "memory");
    }
    TS(10);
    TS(11);
    TSG(23);
}

typedef CUresult (*EncodeTiledFn)(CUtensorMap*, CUtensorMapDataType, cuuint32_t, void*, const cuuint64_t*, const cuuint64_t*,
                                  const cuuint32_t*, const cuuint32_t*, CUtensorMapInterleave, CUtensorMapSwizzle,
                                  CUtensorMapL2promotion, CUtensorMapFloatOOBfill);

}

extern "C" void kernel_launch(void* const* d_in, const int* in_sizes, int n_in, void* d_out, int out_size) {
    (void)in_sizes; (void)n_in; (void)out_size;
    static EncodeTiledFn encode = nullptr;
    static void *qx, *ox, *epoch;
    if (!encode) {
        cudaGetSymbolAddress(&qx, g_qx);
        cudaGetSymbolAddress(&ox, g_ox);
        cudaGetSymbolAddress(&epoch, g_epoch);
        cudaDriverEntryPointQueryResult qr;
        cudaGetDriverEntryPoint("cuTensorMapEncodeTiled", (void**)&encode, cudaEnableDefault, &qr);
        cudaFuncSetAttribute(fused_decode_kernel, cudaFuncAttributeMaxDynamicSharedMemorySize, SM_TOTAL);
    }
    Params p;
    for (int br = 0; br < 2; ++br) {
        p.x[br] = (const __nv_bfloat16*)d_in[br * 5 + 0];
        p.k[br] = (const __nv_bfloat16*)d_in[br * 5 + 1];
        p.v[br] = (const __nv_bfloat16*)d_in[br * 5 + 2];
        const cuuint32_t es[2] = {1, 1};
        {
            const cuuint64_t gd[2] = {4096, (cuuint64_t)D_MODEL};
            const cuuint64_t gs[1] = {4096 * 2};
            const cuuint32_t bd[2] = {64, (cuuint32_t)WQ_ROWS};
            encode(&p.wq[br], CU_TENSOR_MAP_DATA_TYPE_BFLOAT16, 2, d_in[br * 5 + 3], gd, gs, bd, es,
                   CU_TENSOR_MAP_INTERLEAVE_NONE, CU_TENSOR_MAP_SWIZZLE_128B, CU_TENSOR_MAP_L2_PROMOTION_NONE,
                   CU_TENSOR_MAP_FLOAT_OOB_FILL_NONE);
        }
        {
            const cuuint64_t gd[2] = {(cuuint64_t)D_MODEL, 4096};
            const cuuint64_t gs[1] = {D_MODEL * 2};
            const cuuint32_t bd[2] = {WO_PITCH / 2, (cuuint32_t)(WO_ROWS / WSUB)};
            encode(&p.wo[br], CU_TENSOR_MAP_DATA_TYPE_BFLOAT16, 2, d_in[br * 5 + 4], gd, gs, bd, es,
                   CU_TENSOR_MAP_INTERLEAVE_NONE, CU_TENSOR_MAP_SWIZZLE_NONE, WO_PROMO,
                   CU_TENSOR_MAP_FLOAT_OOB_FILL_NONE);
        }
    }
    p.out = (__nv_bfloat16*)d_out;
    p.qx = (unsigned long long*)qx; p.ox = (unsigned long long*)ox; p.epoch = (unsigned int*)epoch;
    fused_decode_kernel<<<NCTA, NTHREADS, SM_TOTAL>>>(p);
}
```

```cpp
#include <cuda_runtime.h>
#include <cuda.h>
#include <cuda_bf16.h>
#include <stdint.h>

namespace {

constexpr int D_MODEL = 576;
constexpr int HKV = 16;
constexpr int SK = 8192;
constexpr int WIN = 2048;
constexpr int NCTA = 128;
constexpr int NWARP = 8;
constexpr int NTHREADS = (NWARP + 1 + 4) * 32;
constexpr int TILE_BYTES = 16384;
constexpr int TPW = WIN / 64 / NWARP;
constexpr int NTILES = 2 * WIN / 64;
constexpr int WQ_CH = 3, WQ_ROWS = 192, WQ_BYTES = WQ_ROWS * 128;
constexpr int WO_PITCH = 288;
constexpr int WO_CH = 4, WO_ROWS = 256 / WO_CH, WO_BYTES = WO_ROWS * WO_PITCH;
constexpr int WSUB = 2;
constexpr int GATE = 4;
constexpr int OPOLL_AFTER = 1;
constexpr int POLL_SLEEP = 32;
constexpr int X_PITCH = 1168, O_PITCH = 576;

constexpr int SM_W = 0;
constexpr int SM_X = SM_W + 256 * WO_PITCH;
constexpr int SM_QS = SM_X + 4 * X_PITCH;
constexpr int SM_OS = SM_QS + 512;
constexpr int SM_ML = SM_OS + 4 * O_PITCH;
constexpr int SM_EP = SM_ML + NWARP * 16;
constexpr int SM_BAR = SM_EP + 16;
constexpr int BAR_FULL = 0, BAR_EMPTY = 8, BAR_WQ = 16, BAR_WO = 19, BAR_ML = BAR_WO + WO_CH, BAR_O = BAR_ML + 1, NBAR = BAR_O + 4;
constexpr int SM_FIXED = SM_BAR + NBAR * 8;
constexpr int SM_TOTAL = SM_FIXED + 2047 + NWARP * TILE_BYTES;
constexpr uint64_t EVICT_FIRST = 0x12F0000000000000ull;

struct Params {
    CUtensorMap wq[2];
    CUtensorMap wo[2];
    const __nv_bfloat16* x[2];
    const __nv_bfloat16* k[2];
    const __nv_bfloat16* v[2];
    __nv_bfloat16* out;
    unsigned long long* qx;
    unsigned long long* ox;
    unsigned int* epoch;
    uint32_t pace;
    uint32_t t0;
};

__device__ __align__(128) unsigned long long g_qx[32 * 4 * 128];
__device__ __align__(128) unsigned long long g_ox[32 * 4 * 128];
__device__ unsigned int g_epoch[NCTA + 8];

__device__ __forceinline__ uint32_t smem_u32(const void* p) { return (uint32_t)__cvta_generic_to_shared(p); }

__device__ __forceinline__ void mbar_init(uint32_t bar, uint32_t cnt) {
    asm volatile("mbarrier.init.shared::cta.b64 [%0], %1;" ::"r"(bar), "r"(cnt) : "memory");
}
__device__ __forceinline__ void mbar_expect_tx(uint32_t bar, uint32_t bytes) {
    asm volatile("mbarrier.arrive.expect_tx.shared::cta.b64 _, [%0], %1;" ::"r"(bar), "r"(bytes) : "memory");
}
__device__ __forceinline__ void mbar_arrive(uint32_t bar) {
    asm volatile("mbarrier.arrive.shared::cta.b64 _, [%0];" ::"r"(bar) : "memory");
}
__device__ __forceinline__ void mbar_wait(uint32_t bar, uint32_t parity) {
#pragma unroll 1
    for (int it = 0; it < (1 << 22); ++it) {
        uint32_t ok;
        asm volatile(
            "{\n.reg .pred p;\n"
            "mbarrier.try_wait.parity.shared::cta.b64 p, [%1], %2;\n"
            "selp.u32 %0, 1, 0, p;\n}\n"
            : "=r"(ok) : "r"(bar), "r"(parity) : "memory");
        if (ok) break;
    }
}
__device__ __forceinline__ bool mbar_test(uint32_t bar, uint32_t parity) {
    uint32_t ok;
    asm volatile(
        "{\n.reg .pred p;\n"
        "mbarrier.test_wait.parity.shared::cta.b64 p, [%1], %2;\n"
        "selp.u32 %0, 1, 0, p;\n}\n"
        : "=r"(ok) : "r"(bar), "r"(parity) : "memory");
    return ok != 0;
}
__device__ __forceinline__ void bulk_load(uint32_t dst, const void* src, uint32_t bytes, uint32_t bar, uint64_t pol) {
    asm volatile(
        "cp.async.bulk.shared::cluster.global.mbarrier::complete_tx::bytes.L2::cache_hint [%0], [%1], %2, [%3], %4;"
        ::"r"(dst), "l"(src), "r"(bytes), "r"(bar), "l"(pol) : "memory");
}
__device__ __forceinline__ void tma_load_2d(uint32_t dst, const CUtensorMap* tm, int c0, int c1, uint32_t bar, uint64_t pol) {
    asm volatile(
        "cp.async.bulk.tensor.2d.shared::cluster.global.mbarrier::complete_tx::bytes.L2::cache_hint "
        "[%0], [%1, {%3, %4}], [%2], %5;"
        ::"r"(dst), "l"(tm), "r"(bar), "r"(c0), "r"(c1), "l"(pol) : "memory");
}
__device__ __forceinline__ void wait_until(uint32_t t) {
#pragma unroll 1
    for (int it = 0; it < (1 << 20); ++it) {
        uint32_t now;
        asm volatile("mov.u32 %0, %globaltimer_lo;" : "=r"(now));
        if ((int)(now - t) >= 0) break;
    }
}
__device__ __forceinline__ void consumer_sync() { asm volatile("bar.sync 1, 256;" ::: "memory"); }

__device__ __forceinline__ void ldsm_x4(uint32_t (&r)[4], uint32_t addr) {
    asm volatile("ldmatrix.sync.aligned.m8n8.x4.shared.b16 {%0,%1,%2,%3}, [%4];"
                 : "=r"(r[0]), "=r"(r[1]), "=r"(r[2]), "=r"(r[3]) : "r"(addr) : "memory");
}
__device__ __forceinline__ void ldsm_x4_t(uint32_t (&r)[4], uint32_t addr) {
    asm volatile("ldmatrix.sync.aligned.m8n8.x4.trans.shared.b16 {%0,%1,%2,%3}, [%4];"
                 : "=r"(r[0]), "=r"(r[1]), "=r"(r[2]), "=r"(r[3]) : "r"(addr) : "memory");
}
__device__ __forceinline__ void mma16816(float (&d)[4], uint32_t a0, uint32_t a1, uint32_t a2, uint32_t a3,
                                         uint32_t b0, uint32_t b1) {
    asm volatile(
        "mma.sync.aligned.m16n8k16.row.col.f32.bf16.bf16.f32 {%0,%1,%2,%3}, {%4,%5,%6,%7}, {%8,%9}, {%0,%1,%2,%3};"
        : "+f"(d[0]), "+f"(d[1]), "+f"(d[2]), "+f"(d[3])
        : "r"(a0), "r"(a1), "r"(a2), "r"(a3), "r"(b0), "r"(b1));
}
__device__ __forceinline__ float ex2(float x) {
    float y;
    asm("ex2.approx.ftz.f32 %0, %1;" : "=f"(y) : "f"(x));
    return y;
}
__device__ __forceinline__ uint32_t pack_bf16(float lo, float hi) {
    uint32_t r;
    asm("cvt.rn.bf16x2.f32 %0, %1, %2;" : "=r"(r) : "f"(hi), "f"(lo));
    return r;
}
__device__ __forceinline__ void ll_store(unsigned long long* p, uint32_t data, uint32_t tag) {
    asm volatile("{\n.reg .b64 v;\nmov.b64 v, {%1, %2};\nst.relaxed.gpu.global.b64 [%0], v;\n}" ::"l"(p), "r"(data), "r"(tag) : "memory");
}
__device__ __forceinline__ void ll_load2(uint32_t (&d)[4], const unsigned long long* p) {
    asm volatile("{\n.reg .b64 u, v;\nld.relaxed.gpu.global.v2.b64 {u, v}, [%4];\nmov.b64 {%0, %1}, u;\nmov.b64 {%2, %3}, v;\n}"
                 : "=r"(d[0]), "=r"(d[1]), "=r"(d[2]), "=r"(d[3]) : "l"(p) : "memory");
}
constexpr int SPIN_MAX = 1 << 21;
__device__ __forceinline__ uint32_t ll_wait(const unsigned long long* p, uint32_t tag) {
    uint32_t d = 0, f;
#pragma unroll 1
    for (int it = 0; it < SPIN_MAX; ++it) {
        asm volatile("{\n.reg .b64 v;\nld.relaxed.gpu.global.b64 v, [%2];\nmov.b64 {%0, %1}, v;\n}" : "=r"(d), "=r"(f) : "l"(p) : "memory");
        if (f == tag) break;
        __nanosleep(POLL_SLEEP);
    }
    return d;
}

__global__ void __launch_bounds__(NTHREADS, 1) fused_decode_kernel(const __grid_constant__ Params p) {
    extern __shared__ __align__(1024) unsigned char smem[];
    const uint32_t sb = smem_u32(smem);
    const uint32_t bars = sb + SM_BAR;
    if (threadIdx.x == 0) {
        const CUtensorMap* tmq = &p.wq[blockIdx.x >> 6];
#pragma unroll
        for (int c = 0; c < WQ_CH; ++c) {
            mbar_init(bars + (BAR_WQ + c) * 8, 1);
            asm volatile("fence.mbarrier_init.release.cluster;" ::: "memory");
            mbar_expect_tx(bars + (BAR_WQ + c) * 8, WQ_BYTES);
            tma_load_2d(sb + SM_W + c * WQ_BYTES, tmq, (blockIdx.x & 63) * 64, c * WQ_ROWS, bars + (BAR_WQ + c) * 8, EVICT_FIRST);
        }
    }
    uint32_t tstart = 0;
    if ((threadIdx.x >> 5) == NWARP) {
        asm volatile("mov.u32 %0, %globaltimer_lo;" : "=r"(tstart));
    } else if (threadIdx.x >= 32 && threadIdx.x < 352) {
        const uint32_t xi = threadIdx.x - (threadIdx.x < 256 ? 32 : 64);
        asm volatile("cp.async.cg.shared.global [%0], [%1], 16;"
                     ::"r"(sb + SM_X + (xi / 72u) * 16 + xi * 16), "l"((const char*)p.x[blockIdx.x >> 6] + xi * 16) : "memory");
    } else if (threadIdx.x == 352) {
        asm volatile("cp.async.ca.shared.global [%0], [%1], 4;" ::"r"(sb + SM_EP), "l"(p.epoch + blockIdx.x) : "memory");
    }
    const uint32_t ring = (sb + SM_FIXED + 2047u) & ~2047u;
    unsigned char* const ringp = smem + (ring - sb);
    const int tid = threadIdx.x, w = tid >> 5, lane = tid & 31;
    const int g = lane >> 2, t = lane & 3;
    const int mat = lane >> 3, i8 = lane & 7;
    const int cta = blockIdx.x;
    const int br = cta >> 6, kvh = (cta >> 2) & 15, b = cta & 3;
    const int grp = cta >> 2;
    __nv_bfloat16* out_dst = p.out + (g & 3) * 1152 + br * 576 + b * 144 + w * 16 + (g >> 2) * 8 + 2 * t;

    if (w > NWARP) {
        const int c = w - NWARP - 1, l16 = lane & 15;
        const int s0 = (b + 1 + (lane >> 4)) & 3, s1 = (b + 3) & 3;
        const unsigned long long* src0 = p.ox + (grp * 4 + s0) * 128 + c * 32 + l16 * 2;
        const unsigned long long* src1 = p.ox + (grp * 4 + s1) * 128 + c * 32 + l16 * 2;
        const uint32_t dst0 = sb + SM_OS + s0 * O_PITCH + c * 128 + l16 * 8, dst1 = sb + SM_OS + s1 * O_PITCH + c * 128 + l16 * 8;
        if (c == 3 && kvh == 0) {
#pragma unroll 1
            for (int i = lane; i < 72; i += 32)
                *(uint4*)(p.out + (i / 18) * 1152 + br * 576 + b * 144 + (i % 18) * 8) = make_uint4(0u, 0u, 0u, 0u);
        }
        asm volatile("cp.async.wait_all;" ::: "memory");
        asm volatile("bar.sync 2, %0;" ::"n"(NTHREADS) : "memory");
        uint32_t tag = *(const volatile uint32_t*)(smem + SM_EP) + 1u;
        if (tag == 0u) tag = 1u;
        if (c == 3) {
            unsigned int* const flag = p.epoch + NCTA + br * 4 + b;
            if (kvh == 0 && lane == 0) asm volatile("st.release.gpu.global.b32 [%0], %1;" ::"l"(flag), "r"(tag) : "memory");
            mbar_wait(bars + BAR_ML * 8, 0);
            if (lane == 0) {
#pragma unroll 1
                for (int it = 0; it < SPIN_MAX; ++it) {
                    uint32_t f;
                    asm volatile("ld.acquire.gpu.global.b32 %0, [%1];" : "=r"(f) : "l"(flag) : "memory");
                    if (f == tag) break;
                    __nanosleep(256);
                }
            }
            __syncwarp();
        }
        mbar_wait(bars + (BAR_WO + OPOLL_AFTER) * 8, 0);
        uint32_t d0[4], d1[4];
#pragma unroll 1
        for (int it = 0; it < SPIN_MAX; ++it) {
            ll_load2(d0, src0);
            ll_load2(d1, src1);
            if (__all_sync(0xffffffffu, d0[1] == tag && d0[3] == tag && d1[1] == tag && d1[3] == tag)) break;
            __nanosleep(POLL_SLEEP);
        }
        asm volatile("st.shared.v2.b32 [%0], {%1, %2};" ::"r"(dst0), "r"(d0[0]), "r"(d0[2]) : "memory");
        asm volatile("st.shared.v2.b32 [%0], {%1, %2};" ::"r"(dst1), "r"(d1[0]), "r"(d1[2]) : "memory");
        __syncwarp();
        if (lane == 0) mbar_arrive(bars + (BAR_O + c) * 8);
        return;
    }
    if (w == NWARP) {
        const size_t kvoff = ((size_t)(b * HKV + kvh) * SK + (SK - WIN)) * 256;
        const char* kbase = (const char*)p.k[br] + kvoff;
        const char* vbase = (const char*)p.v[br] + kvoff - (size_t)(NTILES / 2) * TILE_BYTES;
        const CUtensorMap* tmo = &p.wo[br];
        if (lane == 0) {
#pragma unroll
            for (int i = 0; i < BAR_ML; ++i)
                if (i < BAR_WQ || i >= BAR_WO) mbar_init(bars + i * 8, 1);
            mbar_init(bars + BAR_ML * 8, NWARP);
#pragma unroll
            for (int c = 0; c < 4; ++c) mbar_init(bars + (BAR_O + c) * 8, 2);
            asm volatile("fence.mbarrier_init.release.cluster;" ::: "memory");
            asm volatile("prefetch.tensormap [%0];" ::"l"(tmo) : "memory");
        }
        __syncwarp();
        asm volatile("bar.arrive 2, %0;" ::"n"(NTHREADS) : "memory");
        if (lane == 0) {
            const uint32_t pace = p.pace;
            uint32_t tnext = tstart + p.t0;
#pragma unroll 1
            for (int n = 0; n < NTILES; ++n) {
                const int s = n & 7;
                if (n >= 8) mbar_wait(bars + (BAR_EMPTY + s) * 8, ((n >> 3) - 1) & 1);
                mbar_expect_tx(bars + (BAR_FULL + s) * 8, TILE_BYTES);
                const int tile = ((n & 0x2b) | ((n & 4) << 2) | ((n & 16) >> 2)) ^ (br * 16);
                const char* src = (n < NTILES / 2 ? kbase : vbase) + (size_t)tile * TILE_BYTES;
                wait_until(tnext);
                bulk_load(ring + s * TILE_BYTES, src, TILE_BYTES, bars + (BAR_FULL + s) * 8, EVICT_FIRST);
                tnext += pace;
            }
            const uint32_t step = (pace * 9) / (8 * WSUB);
#pragma unroll 1
            for (int c = 0; c < WO_CH * WSUB; ++c) {
                if (c % WSUB == 0) mbar_expect_tx(bars + (BAR_WO + c / WSUB) * 8, WO_BYTES);
                if (c == GATE && !mbar_test(bars + (BAR_FULL + 7) * 8, 1)) {
                    mbar_wait(bars + (BAR_FULL + 7) * 8, 1);
                    uint32_t now;
                    asm volatile("mov.u32 %0, %globaltimer_lo;" : "=r"(now));
                    if ((int)(now - tnext) > 0) tnext = now;
                }
                wait_until(tnext);
                tnext += step;
                tma_load_2d(sb + SM_W + c * (WO_BYTES / WSUB), tmo, b * 144, kvh * 256 + c * (WO_ROWS / WSUB),
                            bars + (BAR_WO + c / WSUB) * 8, EVICT_FIRST);
            }
        }
        __syncwarp();
    } else {
        unsigned long long* const qx_dst = p.qx + (grp * 4 + (g & 3)) * 128 + b * 32 + w * 4 + t;
        const int opos = (tid & 112) + (tid & 3) * 4 + ((tid >> 2) & 3);
        unsigned long long* const ox_dst = p.ox + (grp * 4 + b) * 128 + opos;
        {
            if (g < 4) ll_store(qx_dst, 0u, 0u);
            if (tid < 128) ll_store(ox_dst, 0u, 0u);
            asm volatile("cp.async.wait_all;" ::: "memory");
            asm volatile("bar.sync 2, %0;" ::"n"(NTHREADS) : "memory");
        }
        uint32_t tag = *(const volatile uint32_t*)(smem + SM_EP) + 1u;
        if (tag == 0u) tag = 1u;
        if (tid == 64) p.epoch[cta] = tag;

        {
            float qa[4] = {0.f, 0.f, 0.f, 0.f}, qb[4] = {0.f, 0.f, 0.f, 0.f};
            uint32_t xaddr = sb + SM_X + (i8 & 3) * X_PITCH + mat * 16;
            uint32_t waddr = sb + SM_W + lane * 128 + ((w ^ i8) << 4);
#pragma unroll 1
            for (int c = 0; c < WQ_CH; ++c) {
                mbar_wait(bars + (BAR_WQ + c) * 8, 0);
#pragma unroll
                for (int kk = 0; kk < WQ_ROWS / 32; ++kk) {
                    uint32_t xa[4], wb[4];
                    ldsm_x4(xa, xaddr + kk * 64);
                    ldsm_x4_t(wb, waddr + kk * 32 * 128);
                    mma16816(qa, xa[0], xa[0], xa[1], xa[1], wb[0], wb[1]);
                    mma16816(qb, xa[2], xa[2], xa[3], xa[3], wb[2], wb[3]);
                }
                xaddr += WQ_ROWS * 2;
                waddr += WQ_BYTES;
            }
            if (g < 4) ll_store(qx_dst, pack_bf16(qa[0] + qb[0], qa[1] + qb[1]), tag);
        }
        if (tid < 128) {
            const uint32_t qw = ll_wait(p.qx + (grp * 4 + b) * 128 + tid, tag);
            ((uint32_t*)(smem + SM_QS))[tid] = qw;
        }
        consumer_sync();

        uint32_t qf[2][16];
        {
            const uint32_t* qs = (const uint32_t*)(smem + SM_QS);
#pragma unroll
            for (int h = 0; h < 2; ++h)
#pragma unroll
                for (int c = 0; c < 16; ++c) qf[h][c] = qs[h * 64 + ((c ^ g) << 2) + t];
        }

        const uint32_t slot = ring + w * TILE_BYTES;
        const uint32_t bfull = bars + (BAR_FULL + w) * 8, bempty = bars + (BAR_EMPTY + w) * 8;
        const uint32_t lbase = slot + ((mat & 1) * 8 + i8) * 256 + (((mat >> 1) ^ i8) << 4);
        const int myj = t ^ (g >> 1);
        const bool odd = (g & 1) != 0;

        float sc[TPW][4];
#pragma unroll
        for (int i = 0; i < TPW; ++i) sc[i][0] = sc[i][1] = sc[i][2] = sc[i][3] = 0.f;
#pragma unroll 1
        for (int i = 0; i < TPW; ++i) {
            mbar_wait(bfull, i & 1);
            float s00 = 0.f, s10 = 0.f, s01 = 0.f, s11 = 0.f;
#pragma unroll
            for (int j = 0; j < 4; ++j) {
                float d0[4] = {0.f, 0.f, 0.f, 0.f}, d1[4] = {0.f, 0.f, 0.f, 0.f};
#pragma unroll
                for (int s = 0; s < 8; ++s) {
                    uint32_t a[4];
                    ldsm_x4(a, (lbase ^ (32 * (s ^ j))) + 4096 * j);
                    mma16816(d0, a[0], a[1], a[2], a[3], qf[0][2 * s], qf[0][2 * s + 1]);
                    mma16816(d1, a[0], a[1], a[2], a[3], qf[1][2 * s], qf[1][2 * s + 1]);
                }
                if (j == myj) {
                    s00 = odd ? d0[1] : d0[0];
                    s01 = odd ? d0[3] : d0[2];
                    s10 = odd ? d1[1] : d1[0];
                    s11 = odd ? d1[3] : d1[2];
                }
            }
            __syncwarp();
            if (lane == 0) mbar_arrive(bempty);
#pragma unroll
            for (int u = 0; u + 1 < TPW; ++u) {
#pragma unroll
                for (int q = 0; q < 4; ++q) sc[u][q] = sc[u + 1][q];
            }
            sc[TPW - 1][0] = s00; sc[TPW - 1][1] = s10; sc[TPW - 1][2] = s01; sc[TPW - 1][3] = s11;
        }

        const float cs = 0.08838834764831845f * 1.4426950408889634f;
        float m0 = -INFINITY, m1 = -INFINITY;
#pragma unroll
        for (int i = 0; i < TPW; ++i) {
            m0 = fmaxf(m0, fmaxf(sc[i][0], sc[i][2]));
            m1 = fmaxf(m1, fmaxf(sc[i][1], sc[i][3]));
        }
#pragma unroll
        for (int o = 16; o > 0; o >>= 1) {
            m0 = fmaxf(m0, __shfl_xor_sync(0xffffffffu, m0, o));
            m1 = fmaxf(m1, __shfl_xor_sync(0xffffffffu, m1, o));
        }
        m0 *= cs; m1 *= cs;
        float l0 = 0.f, l1 = 0.f;
        uint32_t pa[TPW][4];
#pragma unroll
        for (int i = 0; i < TPW; ++i) {
#pragma unroll
            for (int q = 0; q < 4; ++q) {
                const float pv = ex2(fmaf(sc[i][q], cs, (q & 1) ? -m1 : -m0));
                if (q & 1) l1 += pv; else l0 += pv;
                pa[i][q] = pack_bf16(pv, pv);
            }
        }
#pragma unroll
        for (int o = 16; o > 0; o >>= 1) {
            l0 += __shfl_xor_sync(0xffffffffu, l0, o);
            l1 += __shfl_xor_sync(0xffffffffu, l1, o);
        }
        if (lane == 0) {
            ((float4*)(smem + SM_ML))[w] = make_float4(m0, l0, m1, l1);
            mbar_arrive(bars + BAR_ML * 8);
        }

        const uint32_t halfmask = odd ? 0xffff0000u : 0x0000ffffu;
        float f0 = 0.f, f1 = 0.f;
        float acc[16][4];
#pragma unroll
        for (int c = 0; c < 16; ++c) { acc[c][0] = acc[c][1] = acc[c][2] = acc[c][3] = 0.f; }
#pragma unroll 1
        for (int i = 0; i < TPW; ++i) {
            if (i == TPW - 1) {
                mbar_wait(bars + BAR_ML * 8, 0);
                const float4 mine = ((const float4*)(smem + SM_ML))[i8];
                float M0 = mine.x, M1 = mine.z;
#pragma unroll
                for (int o = 4; o > 0; o >>= 1) {
                    M0 = fmaxf(M0, __shfl_xor_sync(0xffffffffu, M0, o));
                    M1 = fmaxf(M1, __shfl_xor_sync(0xffffffffu, M1, o));
                }
                float L0 = ex2(mine.x - M0) * mine.y, L1 = ex2(mine.z - M1) * mine.w;
#pragma unroll
                for (int o = 4; o > 0; o >>= 1) {
                    L0 += __shfl_xor_sync(0xffffffffu, L0, o);
                    L1 += __shfl_xor_sync(0xffffffffu, L1, o);
                }
                f0 = __fdividef(ex2(m0 - M0), L0);
                f1 = __fdividef(ex2(m1 - M1), L1);
            }
            mbar_wait(bfull, i & 1);
#pragma unroll
            for (int j = 0; j < 4; ++j) {
                const uint32_t msk = (j == myj) ? halfmask : 0u;
                const uint32_t a0 = pa[0][0] & msk, a1 = pa[0][1] & msk, a2 = pa[0][2] & msk, a3 = pa[0][3] & msk;
#pragma unroll
                for (int s = 0; s < 8; ++s) {
                    uint32_t bb[4];
                    ldsm_x4_t(bb, (lbase ^ (32 * (s ^ j)) ^ (512 * j)) + 4096 * j);
                    mma16816(acc[2 * s], a0, a1, a2, a3, bb[0], bb[1]);
                    mma16816(acc[2 * s + 1], a0, a1, a2, a3, bb[2], bb[3]);
                }
            }
            __syncwarp();
            if (lane == 0) mbar_arrive(bempty);
#pragma unroll
            for (int u = 0; u + 1 < TPW; ++u) {
#pragma unroll
                for (int q = 0; q < 4; ++q) pa[u][q] = pa[u + 1][q];
            }
        }

#pragma unroll
        for (int c = 0; c < 16; ++c)
            if ((c & 4) == 0) {
#pragma unroll
                for (int q = 0; q < 4; ++q) acc[c][q] += __shfl_xor_sync(0xffffffffu, acc[c ^ 4][q], 16);
            }
#pragma unroll
        for (int c = 0; c < 16; ++c)
            if ((c & 6) == 0) {
#pragma unroll
                for (int q = 0; q < 4; ++q) acc[c][q] += __shfl_xor_sync(0xffffffffu, acc[c ^ 2][q], 8);
            }
#pragma unroll
        for (int c = 0; c < 16; c += 8) {
#pragma unroll
            for (int q = 0; q < 4; ++q) acc[c][q] += __shfl_xor_sync(0xffffffffu, acc[c ^ 1][q], 4);
        }
        {
            float2* ow = (float2*)(ringp + w * TILE_BYTES);
            ow[lane] = make_float2(acc[0][0] * f0, acc[0][1] * f0);
            ow[32 + lane] = make_float2(acc[8][0] * f0, acc[8][1] * f0);
            ow[64 + lane] = make_float2(acc[0][2] * f1, acc[0][3] * f1);
            ow[96 + lane] = make_float2(acc[8][2] * f1, acc[8][3] * f1);
        }
        consumer_sync();
        if (tid < 128) {
            float o0 = 0.f, o1 = 0.f;
#pragma unroll
            for (int ww = 0; ww < NWARP; ++ww) {
                const float2 v = ((const float2*)(ringp + ww * TILE_BYTES))[tid];
                o0 += v.x; o1 += v.y;
            }
            const uint32_t ow = pack_bf16(o0, o1);
            ll_store(ox_dst, ow, tag);
            ((uint32_t*)(smem + SM_OS + b * O_PITCH))[opos] = ow;
            __syncwarp();
            if (lane == 0) mbar_arrive(bars + (BAR_O + w) * 8);
        }
    }
    {
        uint32_t abase = sb + SM_W + ((mat >> 1) * 8 + i8) * WO_PITCH + (((mat & 1) ^ (i8 >> 2)) << 4) + w * 32;
        const uint32_t ouse = (g < 4) == (t < 2);
        uint32_t old = sb + SM_OS + (g & 3) * O_PITCH + t * 16;
        asm volatile("" : "+r"(abase), "+r"(old), "+l"(out_dst));
        uint32_t wa[4][4][4], ob[4][2][4];
        float oa[4][4];
#pragma unroll
        for (int i = 0; i < 4; ++i) {
            oa[i][0] = oa[i][1] = oa[i][2] = oa[i][3] = 0.f;
#pragma unroll
            for (int u = 0; u < 2; ++u) ob[i][u][0] = ob[i][u][1] = ob[i][u][2] = ob[i][u][3] = 0u;
        }
        auto load_w = [&](int c) {
#pragma unroll
            for (int kk = 0; kk < 4; ++kk) ldsm_x4_t(wa[c][kk], abase + (c * 4 + kk) * 16 * WO_PITCH);
        };
        auto load_o = [&](int c) {
#pragma unroll
            for (int u = 0; u < 2; ++u)
                asm volatile("{\n.reg .pred p;\nsetp.ne.u32 p, %5, 0;\n@p ld.shared.v4.b32 {%0, %1, %2, %3}, [%4];\n}"
                             : "+r"(ob[c][u][0]), "+r"(ob[c][u][1]), "+r"(ob[c][u][2]), "+r"(ob[c][u][3])
                             : "r"(old + c * 128 + u * 64), "r"(ouse) : "memory");
        };
        auto mul = [&](int c) {
#pragma unroll
            for (int kk = 0; kk < 4; ++kk)
                mma16816(oa[kk], wa[c][kk][0], wa[c][kk][1], wa[c][kk][2], wa[c][kk][3], ob[c][kk >> 1][(kk & 1) * 2],
                         ob[c][kk >> 1][(kk & 1) * 2 + 1]);
        };
        mbar_wait(bars + (BAR_WO + 0) * 8, 0);
        load_w(0);
        mbar_wait(bars + (BAR_WO + 1) * 8, 0);
        load_w(1);
        bool o0 = false, o1 = false, o2 = false, o3 = false, w2 = false, w3 = false;
#pragma unroll 1
        for (int it = 0; it < (1 << 24); ++it) {
            if (!o0 && mbar_test(bars + (BAR_O + 0) * 8, 0)) { load_o(0); mul(0); o0 = true; }
            if (!o1 && mbar_test(bars + (BAR_O + 1) * 8, 0)) { load_o(1); mul(1); o1 = true; }
            if (!o2 && mbar_test(bars + (BAR_O + 2) * 8, 0)) { load_o(2); o2 = true; }
            if (!o3 && mbar_test(bars + (BAR_O + 3) * 8, 0)) { load_o(3); o3 = true; }
            if (o0 && o1 && o2 && o3) break;
            if (!w2) {
                if (mbar_test(bars + (BAR_WO + 2) * 8, 0)) { load_w(2); w2 = true; }
            } else if (mbar_test(bars + (BAR_WO + 3) * 8, 0)) {
                load_w(3);
                w3 = true;
                break;
            }
        }
        if (!w3) {
            if (!w2) { mbar_wait(bars + (BAR_WO + 2) * 8, 0); load_w(2); }
            mul(2);
            mbar_wait(bars + (BAR_WO + 3) * 8, 0);
            load_w(3);
            mul(3);
        } else {
            if (o2) mul(2);
            if (o3) mul(3);
            if (!o0) { mbar_wait(bars + (BAR_O + 0) * 8, 0); load_o(0); mul(0); }
            if (!o1) { mbar_wait(bars + (BAR_O + 1) * 8, 0); load_o(1); mul(1); }
            if (!o2) { mbar_wait(bars + (BAR_O + 2) * 8, 0); load_o(2); mul(2); }
            if (!o3) { mbar_wait(bars + (BAR_O + 3) * 8, 0); load_o(3); mul(3); }
        }
        const float r0 = ((oa[0][0] + oa[1][0]) + (oa[2][0] + oa[3][0])) +
                         __shfl_xor_sync(0xffffffffu, (oa[0][2] + oa[1][2]) + (oa[2][2] + oa[3][2]), 2);
        const float r1 = ((oa[0][1] + oa[1][1]) + (oa[2][1] + oa[3][1])) +
                         __shfl_xor_sync(0xffffffffu, (oa[0][3] + oa[1][3]) + (oa[2][3] + oa[3][3]), 2);
        uint32_t rt;
        asm volatile("movmatrix.sync.aligned.m8n8.trans.b16 %0, %1;" : "=r"(rt) : "r"(pack_bf16(r0, r1)));
        asm volatile("red.relaxed.gpu.global.add.noftz.bf16x2 [%0], %1;" ::"l"(out_dst), "r"(rt) : "memory");
    }
}

typedef CUresult (*EncodeTiledFn)(CUtensorMap*, CUtensorMapDataType, cuuint32_t, void*, const cuuint64_t*, const cuuint64_t*,
                                  const cuuint32_t*, const cuuint32_t*, CUtensorMapInterleave, CUtensorMapSwizzle,
                                  CUtensorMapL2promotion, CUtensorMapFloatOOBfill);

}

extern "C" void kernel_launch(void* const* d_in, const int* in_sizes, int n_in, void* d_out, int out_size) {
    (void)in_sizes; (void)n_in; (void)out_size;
    static EncodeTiledFn encode = nullptr;
    static void *qx, *ox, *epoch;
    static uint32_t pace = 655;
    if (!encode) {
        int dev = 0, khz = 0, bits = 0;
        cudaGetDevice(&dev);
        cudaDeviceGetAttribute(&khz, cudaDevAttrMemoryClockRate, dev);
        cudaDeviceGetAttribute(&bits, cudaDevAttrGlobalMemoryBusWidth, dev);
        if (khz > 0 && bits > 0) {
            const double bytes_per_ns = 0.955 * 2.0 * khz * 1e-6 * (bits / 8);
            pace = (uint32_t)((double)NCTA * TILE_BYTES / bytes_per_ns + 0.5);
        }
        cudaGetSymbolAddress(&qx, g_qx);
        cudaGetSymbolAddress(&ox, g_ox);
        cudaGetSymbolAddress(&epoch, g_epoch);
        cudaDriverEntryPointQueryResult qr;
        cudaGetDriverEntryPoint("cuTensorMapEncodeTiled", (void**)&encode, cudaEnableDefault, &qr);
        cudaFuncSetAttribute(fused_decode_kernel, cudaFuncAttributeMaxDynamicSharedMemorySize, SM_TOTAL);
    }
    Params p;
    for (int br = 0; br < 2; ++br) {
        p.x[br] = (const __nv_bfloat16*)d_in[br * 5 + 0];
        p.k[br] = (const __nv_bfloat16*)d_in[br * 5 + 1];
        p.v[br] = (const __nv_bfloat16*)d_in[br * 5 + 2];
        const cuuint32_t es[2] = {1, 1};
        {
            const cuuint64_t gd[2] = {4096, (cuuint64_t)D_MODEL};
            const cuuint64_t gs[1] = {4096 * 2};
            const cuuint32_t bd[2] = {64, (cuuint32_t)WQ_ROWS};
            encode(&p.wq[br], CU_TENSOR_MAP_DATA_TYPE_BFLOAT16, 2, d_in[br * 5 + 3], gd, gs, bd, es,
                   CU_TENSOR_MAP_INTERLEAVE_NONE, CU_TENSOR_MAP_SWIZZLE_128B, CU_TENSOR_MAP_L2_PROMOTION_NONE,
                   CU_TENSOR_MAP_FLOAT_OOB_FILL_NONE);
        }
        {
            const cuuint64_t gd[2] = {(cuuint64_t)D_MODEL, 4096};
            const cuuint64_t gs[1] = {D_MODEL * 2};
            const cuuint32_t bd[2] = {WO_PITCH / 2, (cuuint32_t)(WO_ROWS / WSUB)};
            encode(&p.wo[br], CU_TENSOR_MAP_DATA_TYPE_BFLOAT16, 2, d_in[br * 5 + 4], gd, gs, bd, es,
                   CU_TENSOR_MAP_INTERLEAVE_NONE, CU_TENSOR_MAP_SWIZZLE_NONE, CU_TENSOR_MAP_L2_PROMOTION_L2_128B,
                   CU_TENSOR_MAP_FLOAT_OOB_FILL_NONE);
        }
    }
    p.out = (__nv_bfloat16*)d_out;
    p.qx = (unsigned long long*)qx; p.ox = (unsigned long long*)ox; p.epoch = (unsigned int*)epoch;
    p.pace = pace;
    p.t0 = (pace * 11) / 3;
    fused_decode_kernel<<<NCTA, NTHREADS, SM_TOTAL>>>(p);
}
```
